```python
import torch

def _softmax(x, axis=-1):
    return torch.softmax(x, dim=axis)
def _gelu(x):
    return torch.nn.functional.gelu(x, approximate="tanh")
def _silu(x):
    return torch.nn.functional.silu(x)
def _sigmoid(x):
    return torch.sigmoid(x)
def _layernorm(x, axis=-1, eps=1e-5):
    m = x.mean(dim=axis, keepdim=True)
    v = x.var(dim=axis, keepdim=True, unbiased=False)
    return (x - m) / torch.sqrt(v + eps)
def _scatter_add(tgt, idx, src, axis=0):
    return tgt.clone().index_add_(axis, idx, src)
def _segment_sum(src, seg, n):
    out = torch.zeros((n,) + src.shape[1:], dtype=src.dtype)
    return out.index_add_(0, seg, src)
def _pad(x, pw):
    flat = tuple(v for pair in reversed(pw) for v in pair)
    return torch.nn.functional.pad(x, flat)

kernel_name = 'gated_mix__grouped_kv_mqa__sliding_local_dilated__prompt'

def setup_inputs():

    _w = (lambda a: (lambda t: t.to(torch.bfloat16) if t.is_floating_point() else t)(torch.as_tensor(a)))
    def _A_setup():
        B, S, D, H = 1, 2048, 640, 32
        Dh = D // H
        return {
            "x": _w((lambda *s: torch.randn(*s, dtype=torch.bfloat16) * 0.05)(B, S, D)),
            "wq": _w((lambda *s: torch.randn(*s, dtype=torch.bfloat16) * 1.6)(D, H * Dh)),
            "wk": _w((lambda *s: torch.randn(*s, dtype=torch.bfloat16) * 1.6)(D, Dh)),
            "wv": _w((lambda *s: torch.randn(*s, dtype=torch.bfloat16) * 0.2)(D, Dh)),
            "wo": _w((lambda *s: torch.randn(*s, dtype=torch.bfloat16) * 0.2)(H * Dh, D)),
        }
    _A_in = _A_setup()

    def _B_setup():
        B, S, D = 1, 2048, 640
        return {
            "x": _w((lambda *s: torch.randn(*s, dtype=torch.bfloat16) * 0.05)(B, S, D)),
            "wqkv": _w((lambda *s: torch.randn(*s, dtype=torch.bfloat16) * 0.8)(D, 3 * D)),
            "wo": _w((lambda *s: torch.randn(*s, dtype=torch.bfloat16) * 0.05)(D, D)),
        }
    _B_in = _B_setup()

    return {
        "A_x": _A_in["x"],
        "A_wq": _A_in["wq"],
        "A_wk": _A_in["wk"],
        "A_wv": _A_in["wv"],
        "A_wo": _A_in["wo"],
        "B_x": _B_in["x"],
        "B_wqkv": _B_in["wqkv"],
        "B_wo": _B_in["wo"],
        "gate_w": _w((lambda *s: torch.randn(*s, dtype=torch.bfloat16) * 0.05)(640) * 16.0),
    }

def reference(A_x, A_wq, A_wk, A_wv, A_wo, B_x, B_wqkv, B_wo, gate_w):
    def _A_ref(x, wq, wk, wv, wo):
        B, S, D = x.shape
        H = 32
        Dh = D // H
        q = (lambda x, *d: x.permute(*d))((x @ wq).reshape(B, S, H, Dh), 0, 2, 1, 3)
        k = x @ wk
        v = x @ wv
        scores = torch.einsum("bhqd,bkd->bhqk", q, k) * (Dh ** -0.5)
        p = _softmax(scores, axis=-1)
        o = torch.einsum("bhqk,bkd->bhqd", p, v)
        return (lambda x, *d: x.permute(*d))(o, 0, 2, 1, 3).reshape(B, S, H * Dh) @ wo

    def _B_ref(x, wqkv, wo):
        B, S, D = x.shape
        H = 32; Dh = D // H
        W, dil = 8, 2
        qkv = (lambda x, *d: x.permute(*d))((x @ wqkv).reshape(B, S, 3, H, Dh), 2, 0, 3, 1, 4)
        q, k, v = qkv[0], qkv[1], qkv[2]
        scale = Dh ** -0.5
        pos = torch.arange(S)
        off = torch.arange(W) * dil
        idx = pos[:, None] - off[None, :]
        mask = idx >= 0
        idx_c = torch.where(mask, idx, 0).reshape(-1)
        kg = k[:, :, idx_c, :].reshape(B, H, S, W, Dh)
        vg = v[:, :, idx_c, :].reshape(B, H, S, W, Dh)
        logits = torch.einsum("bhsd,bhswd->bhsw", q, kg) * scale
        logits = torch.where(mask[None, None, :, :], logits, -1e9)
        attn = _softmax(logits, axis=-1)
        o = torch.einsum("bhsw,bhswd->bhsd", attn, vg)
        return (lambda x, *d: x.permute(*d))(o, 0, 2, 1, 3).reshape(B, S, D) @ wo

    x = A_x
    g = _sigmoid((x * gate_w).sum(-1, keepdims=True))
    a = _A_ref(x, A_wq, A_wk, A_wv, A_wo)
    b = _B_ref(x, B_wqkv, B_wo)
    return g * a + (1 - g) * b
```

```cpp
#include <cuda_runtime.h>
#include <cuda_bf16.h>
#include <cuda.h>
#include <stdint.h>

namespace {

constexpr int SEQ = 2048;
constexpr int DM = 640;
constexpr int DH = 20;

constexpr float K_SCALE = 0.3225964182229561f;

#define SCM 0xEAEAu
constexpr uint32_t SC_MASK = SCM;

constexpr int KV_BYTES = 16 * 12288;

__device__ __align__(1024) __nv_bfloat16 g_Q[SEQ * DM];
__device__ __align__(1024) __nv_bfloat16 g_QKVB[SEQ * 3 * DM];
__device__ __align__(1024) uint32_t g_KV[KV_BYTES / 4];
__device__ __align__(1024) __nv_bfloat16 g_O[SEQ * 2 * DM];
__device__ __align__(16) float g_gate[SEQ];
__device__ __align__(16) float g_kmax[128];

#define TSTAMP(k, slot) do { } while (0)
__device__ __forceinline__ uint32_t smem_u32(const void* p) { return (uint32_t)__cvta_generic_to_shared(p); }
__device__ __forceinline__ void mbar_init(uint32_t bar, uint32_t cnt) {
    asm volatile("mbarrier.init.shared::cta.b64 [%0], %1;" ::"r"(bar), "r"(cnt) : "memory");
}
__device__ __forceinline__ void mbar_expect_tx(uint32_t bar, uint32_t bytes) {
    asm volatile("mbarrier.arrive.expect_tx.shared::cta.b64 _, [%0], %1;" ::"r"(bar), "r"(bytes) : "memory");
}
__device__ __forceinline__ void mbar_arrive(uint32_t bar) {
    asm volatile("mbarrier.arrive.shared::cta.b64 _, [%0];" ::"r"(bar) : "memory");
}
__device__ __forceinline__ void mbar_arrive_remote(uint32_t bar, uint32_t cta) {
    asm volatile(
        "{\n.reg .b32 ra;\n"
        "mapa.shared::cluster.u32 ra, %0, %1;\n"
        "mbarrier.arrive.shared::cluster.b64 _, [ra];\n}"
        ::"r"(bar), "r"(cta) : "memory");
}
__device__ __forceinline__ void mbar_wait(uint32_t bar, uint32_t parity) {
    asm volatile(
        "{\n.reg .pred p;\n.reg .u32 n;\n"
        "mbarrier.try_wait.parity.shared::cta.b64 p, [%0], %1;\n"
        "@p bra DONE_%=;\n"
        "mov.u32 n, 0;\n"
        "WAIT_%=:\n"
        "mbarrier.try_wait.parity.shared::cta.b64 p, [%0], %1;\n"
        "@p bra DONE_%=;\n"
        "add.u32 n, n, 1;\n"
        "setp.lt.u32 p, n, 0x1000000;\n"
        "@p bra WAIT_%=;\n"
        "trap;\n"
        "DONE_%=:\n}"
        ::"r"(bar), "r"(parity) : "memory");
}
__device__ __forceinline__ void mbar_wait_cluster(uint32_t bar, uint32_t parity) {
    asm volatile(
        "{\n.reg .pred p;\n.reg .u32 n;\n"
        "mov.u32 n, 0;\n"
        "WAIT_%=:\n"
        "mbarrier.try_wait.parity.acquire.cluster.shared::cta.b64 p, [%0], %1;\n"
        "@p bra DONE_%=;\n"
        "add.u32 n, n, 1;\n"
        "setp.lt.u32 p, n, 0x1000000;\n"
        "@p bra WAIT_%=;\n"
        "trap;\n"
        "DONE_%=:\n}"
        ::"r"(bar), "r"(parity) : "memory");
}
__device__ __forceinline__ void mbar_wait_warp(uint32_t bar, uint32_t parity) {
    uint32_t n = 0;
    while (true) {
        uint32_t ok;
        asm volatile(
            "{\n.reg .pred p;\n"
            "mbarrier.try_wait.parity.shared::cta.b64 p, [%1], %2;\n"
            "selp.u32 %0, 1, 0, p;\n}"
            : "=r"(ok) : "r"(bar), "r"(parity) : "memory");
        if (__all_sync(0xffffffffu, ok)) break;
        if (++n > 0x1000000u) __trap();
    }
}
__device__ __forceinline__ void fence_barrier_init() {
    asm volatile("fence.mbarrier_init.release.cluster;" ::: "memory");
}
__device__ __forceinline__ void fence_proxy_async() {
    asm volatile("fence.proxy.async.shared::cta;" ::: "memory");
}
__device__ __forceinline__ void cluster_arrive_relaxed() {
    asm volatile("barrier.cluster.arrive.relaxed.aligned;" ::: "memory");
}
__device__ __forceinline__ void cluster_wait() {
    asm volatile("barrier.cluster.wait.acquire.aligned;" ::: "memory");
}
__device__ __forceinline__ uint32_t cluster_rank() {
    uint32_t r;
    asm volatile("mov.u32 %0, %%cluster_ctarank;" : "=r"(r));
    return r;
}
__device__ __forceinline__ void tma_2d(uint32_t dst, const CUtensorMap* tm, int c0, int c1, uint32_t bar) {
    asm volatile(
        "cp.async.bulk.tensor.2d.shared::cluster.global.mbarrier::complete_tx::bytes [%0], [%1, {%3, %4}], [%2];"
        ::"r"(dst), "l"(tm), "r"(bar), "r"(c0), "r"(c1) : "memory");
}
__device__ __forceinline__ void tma_3d(uint32_t dst, const CUtensorMap* tm, int c0, int c1, int c2, uint32_t bar) {
    asm volatile(
        "cp.async.bulk.tensor.3d.shared::cluster.global.mbarrier::complete_tx::bytes [%0], [%1, {%3, %4, %5}], [%2];"
        ::"r"(dst), "l"(tm), "r"(bar), "r"(c0), "r"(c1), "r"(c2) : "memory");
}
__device__ __forceinline__ void bulk_g2s(uint32_t dst, const void* src, uint32_t bytes, uint32_t bar) {
    asm volatile("cp.async.bulk.shared::cluster.global.mbarrier::complete_tx::bytes [%0], [%1], %2, [%3];"
                 ::"r"(dst), "l"(src), "r"(bytes), "r"(bar) : "memory");
}
__device__ __forceinline__ void prefetch_tmap(const CUtensorMap* tm) {
    asm volatile("prefetch.tensormap [%0];" ::"l"(tm) : "memory");
}
__device__ __forceinline__ uint64_t make_desc(uint32_t addr, uint32_t lbo, uint32_t sbo, uint32_t swz) {
    uint64_t d = 0;
    d |= (uint64_t)((addr & 0x3FFFF) >> 4);
    d |= (uint64_t)((lbo & 0x3FFFF) >> 4) << 16;
    d |= (uint64_t)((sbo & 0x3FFFF) >> 4) << 32;
    d |= (uint64_t)swz << 62;
    return d;
}
__device__ __forceinline__ void wg_fence() { asm volatile("wgmma.fence.sync.aligned;" ::: "memory"); }
__device__ __forceinline__ void wg_commit() { asm volatile("wgmma.commit_group.sync.aligned;" ::: "memory"); }
template <int N>
__device__ __forceinline__ void wg_wait() {
    asm volatile("wgmma.wait_group.sync.aligned %0;" ::"n"(N) : "memory");
}
template <int N>
__device__ __forceinline__ void fence_regs(float (&r)[N]) {
#pragma unroll
    for (int i = 0; i < N; i++) asm volatile("" : "+f"(r[i])::"memory");
}
template <int N>
__device__ __forceinline__ void fence_regs(uint32_t (&r)[N]) {
#pragma unroll
    for (int i = 0; i < N; i++) asm volatile("" : "+r"(r[i])::"memory");
}
__device__ __forceinline__ uint32_t pack_bf16(float lo, float hi) {
    uint32_t r;
    asm("cvt.rn.bf16x2.f32 %0, %1, %2;" : "=r"(r) : "f"(hi), "f"(lo));
    return r;
}
__device__ __forceinline__ float bf_lo(uint32_t w) { return __uint_as_float(w << 16); }
__device__ __forceinline__ float bf_hi(uint32_t w) { return __uint_as_float(w & 0xFFFF0000u); }
__device__ __forceinline__ float ex2_mufu(float x) {
    float y;
    asm("ex2.approx.ftz.f32 %0, %1;" : "=f"(y) : "f"(x));
    return y;
}
__device__ __forceinline__ void named_bar_sync(int id, int n) {
    asm volatile("bar.sync %0, %1;" ::"r"(id), "r"(n) : "memory");
}
__device__ __forceinline__ void griddep_wait() { asm volatile("griddepcontrol.wait;" ::: "memory"); }
__device__ __forceinline__ void griddep_launch() { asm volatile("griddepcontrol.launch_dependents;" ::: "memory"); }

__device__ __forceinline__ void wgmma_n64_rs_z(float (&d)[32], uint32_t a0, uint32_t a1, uint32_t a2, uint32_t a3, uint64_t descB) {
    asm volatile(
        "wgmma.mma_async.sync.aligned.m64n64k16.f32.bf16.bf16 {%0, %1, %2, %3, %4, %5, %6, %7, %8, %9, %10, %11, %12, %13, %14, %15, %16, %17, %18, %19, %20, %21, %22, %23, %24, %25, %26, %27, %28, %29, %30, %31}, {%32, %33, %34, %35}, %36, 0, 1, 1, 0;\n"
        : "=f"(d[0]), "=f"(d[1]), "=f"(d[2]), "=f"(d[3]), "=f"(d[4]), "=f"(d[5]), "=f"(d[6]), "=f"(d[7]), "=f"(d[8]), "=f"(d[9]), "=f"(d[10]), "=f"(d[11]), "=f"(d[12]), "=f"(d[13]), "=f"(d[14]), "=f"(d[15]), "=f"(d[16]), "=f"(d[17]), "=f"(d[18]), "=f"(d[19]), "=f"(d[20]), "=f"(d[21]), "=f"(d[22]), "=f"(d[23]), "=f"(d[24]), "=f"(d[25]), "=f"(d[26]), "=f"(d[27]), "=f"(d[28]), "=f"(d[29]), "=f"(d[30]), "=f"(d[31])
        : "r"(a0), "r"(a1), "r"(a2), "r"(a3), "l"(descB));
}
__device__ __forceinline__ void wgmma_n64_rs(float (&d)[32], uint32_t a0, uint32_t a1, uint32_t a2, uint32_t a3, uint64_t descB) {
    asm volatile(
        "wgmma.mma_async.sync.aligned.m64n64k16.f32.bf16.bf16 {%0, %1, %2, %3, %4, %5, %6, %7, %8, %9, %10, %11, %12, %13, %14, %15, %16, %17, %18, %19, %20, %21, %22, %23, %24, %25, %26, %27, %28, %29, %30, %31}, {%32, %33, %34, %35}, %36, 1, 1, 1, 0;\n"
        : "+f"(d[0]), "+f"(d[1]), "+f"(d[2]), "+f"(d[3]), "+f"(d[4]), "+f"(d[5]), "+f"(d[6]), "+f"(d[7]), "+f"(d[8]), "+f"(d[9]), "+f"(d[10]), "+f"(d[11]), "+f"(d[12]), "+f"(d[13]), "+f"(d[14]), "+f"(d[15]), "+f"(d[16]), "+f"(d[17]), "+f"(d[18]), "+f"(d[19]), "+f"(d[20]), "+f"(d[21]), "+f"(d[22]), "+f"(d[23]), "+f"(d[24]), "+f"(d[25]), "+f"(d[26]), "+f"(d[27]), "+f"(d[28]), "+f"(d[29]), "+f"(d[30]), "+f"(d[31])
        : "r"(a0), "r"(a1), "r"(a2), "r"(a3), "l"(descB));
}
__device__ __forceinline__ void wgmma_n24_rs_tb(float (&d)[12], uint32_t a0, uint32_t a1, uint32_t a2, uint32_t a3, uint64_t descB) {
    asm volatile(
        "wgmma.mma_async.sync.aligned.m64n24k16.f32.bf16.bf16 {%0, %1, %2, %3, %4, %5, %6, %7, %8, %9, %10, %11}, {%12, %13, %14, %15}, %16, 1, 1, 1, 1;\n"
        : "+f"(d[0]), "+f"(d[1]), "+f"(d[2]), "+f"(d[3]), "+f"(d[4]), "+f"(d[5]), "+f"(d[6]), "+f"(d[7]), "+f"(d[8]), "+f"(d[9]), "+f"(d[10]), "+f"(d[11])
        : "r"(a0), "r"(a1), "r"(a2), "r"(a3), "l"(descB));
}
__device__ __forceinline__ void wgmma_n32_ss_tb(float (&d)[16], uint64_t descA, uint64_t descB) {
    asm volatile(
        "wgmma.mma_async.sync.aligned.m64n32k16.f32.bf16.bf16 {%0, %1, %2, %3, %4, %5, %6, %7, %8, %9, %10, %11, %12, %13, %14, %15}, %16, %17, 1, 1, 1, 0, 1;\n"
        : "+f"(d[0]), "+f"(d[1]), "+f"(d[2]), "+f"(d[3]), "+f"(d[4]), "+f"(d[5]), "+f"(d[6]), "+f"(d[7]), "+f"(d[8]), "+f"(d[9]), "+f"(d[10]), "+f"(d[11]), "+f"(d[12]), "+f"(d[13]), "+f"(d[14]), "+f"(d[15])
        : "l"(descA), "l"(descB));
}
__device__ __forceinline__ void wgmma_n48_ss_tb(float (&d)[24], uint64_t descA, uint64_t descB) {
    asm volatile(
        "wgmma.mma_async.sync.aligned.m64n48k16.f32.bf16.bf16 {%0, %1, %2, %3, %4, %5, %6, %7, %8, %9, %10, %11, %12, %13, %14, %15, %16, %17, %18, %19, %20, %21, %22, %23}, %24, %25, 1, 1, 1, 0, 1;\n"
        : "+f"(d[0]), "+f"(d[1]), "+f"(d[2]), "+f"(d[3]), "+f"(d[4]), "+f"(d[5]), "+f"(d[6]), "+f"(d[7]), "+f"(d[8]), "+f"(d[9]), "+f"(d[10]), "+f"(d[11]), "+f"(d[12]), "+f"(d[13]), "+f"(d[14]), "+f"(d[15]), "+f"(d[16]), "+f"(d[17]), "+f"(d[18]), "+f"(d[19]), "+f"(d[20]), "+f"(d[21]), "+f"(d[22]), "+f"(d[23])
        : "l"(descA), "l"(descB));
}
__device__ __forceinline__ void wgmma_n128_ss_tb(float (&d)[64], uint64_t descA, uint64_t descB) {
    asm volatile(
        "wgmma.mma_async.sync.aligned.m64n128k16.f32.bf16.bf16 {%0, %1, %2, %3, %4, %5, %6, %7, %8, %9, %10, %11, %12, %13, %14, %15, %16, %17, %18, %19, %20, %21, %22, %23, %24, %25, %26, %27, %28, %29, %30, %31, %32, %33, %34, %35, %36, %37, %38, %39, %40, %41, %42, %43, %44, %45, %46, %47, %48, %49, %50, %51, %52, %53, %54, %55, %56, %57, %58, %59, %60, %61, %62, %63}, %64, %65, 1, 1, 1, 0, 1;\n"
        : "+f"(d[0]), "+f"(d[1]), "+f"(d[2]), "+f"(d[3]), "+f"(d[4]), "+f"(d[5]), "+f"(d[6]), "+f"(d[7]), "+f"(d[8]), "+f"(d[9]), "+f"(d[10]), "+f"(d[11]), "+f"(d[12]), "+f"(d[13]), "+f"(d[14]), "+f"(d[15]), "+f"(d[16]), "+f"(d[17]), "+f"(d[18]), "+f"(d[19]), "+f"(d[20]), "+f"(d[21]), "+f"(d[22]), "+f"(d[23]), "+f"(d[24]), "+f"(d[25]), "+f"(d[26]), "+f"(d[27]), "+f"(d[28]), "+f"(d[29]), "+f"(d[30]), "+f"(d[31]), "+f"(d[32]), "+f"(d[33]), "+f"(d[34]), "+f"(d[35]), "+f"(d[36]), "+f"(d[37]), "+f"(d[38]), "+f"(d[39]), "+f"(d[40]), "+f"(d[41]), "+f"(d[42]), "+f"(d[43]), "+f"(d[44]), "+f"(d[45]), "+f"(d[46]), "+f"(d[47]), "+f"(d[48]), "+f"(d[49]), "+f"(d[50]), "+f"(d[51]), "+f"(d[52]), "+f"(d[53]), "+f"(d[54]), "+f"(d[55]), "+f"(d[56]), "+f"(d[57]), "+f"(d[58]), "+f"(d[59]), "+f"(d[60]), "+f"(d[61]), "+f"(d[62]), "+f"(d[63])
        : "l"(descA), "l"(descB));
}
__device__ __forceinline__ void wgmma_n192_ss_tb(float (&d)[96], uint64_t descA, uint64_t descB) {
    asm volatile(
        "wgmma.mma_async.sync.aligned.m64n192k16.f32.bf16.bf16 {%0, %1, %2, %3, %4, %5, %6, %7, %8, %9, %10, %11, %12, %13, %14, %15, %16, %17, %18, %19, %20, %21, %22, %23, %24, %25, %26, %27, %28, %29, %30, %31, %32, %33, %34, %35, %36, %37, %38, %39, %40, %41, %42, %43, %44, %45, %46, %47, %48, %49, %50, %51, %52, %53, %54, %55, %56, %57, %58, %59, %60, %61, %62, %63, %64, %65, %66, %67, %68, %69, %70, %71, %72, %73, %74, %75, %76, %77, %78, %79, %80, %81, %82, %83, %84, %85, %86, %87, %88, %89, %90, %91, %92, %93, %94, %95}, %96, %97, 1, 1, 1, 0, 1;\n"
        : "+f"(d[0]), "+f"(d[1]), "+f"(d[2]), "+f"(d[3]), "+f"(d[4]), "+f"(d[5]), "+f"(d[6]), "+f"(d[7]), "+f"(d[8]), "+f"(d[9]), "+f"(d[10]), "+f"(d[11]), "+f"(d[12]), "+f"(d[13]), "+f"(d[14]), "+f"(d[15]), "+f"(d[16]), "+f"(d[17]), "+f"(d[18]), "+f"(d[19]), "+f"(d[20]), "+f"(d[21]), "+f"(d[22]), "+f"(d[23]), "+f"(d[24]), "+f"(d[25]), "+f"(d[26]), "+f"(d[27]), "+f"(d[28]), "+f"(d[29]), "+f"(d[30]), "+f"(d[31]), "+f"(d[32]), "+f"(d[33]), "+f"(d[34]), "+f"(d[35]), "+f"(d[36]), "+f"(d[37]), "+f"(d[38]), "+f"(d[39]), "+f"(d[40]), "+f"(d[41]), "+f"(d[42]), "+f"(d[43]), "+f"(d[44]), "+f"(d[45]), "+f"(d[46]), "+f"(d[47]), "+f"(d[48]), "+f"(d[49]), "+f"(d[50]), "+f"(d[51]), "+f"(d[52]), "+f"(d[53]), "+f"(d[54]), "+f"(d[55]), "+f"(d[56]), "+f"(d[57]), "+f"(d[58]), "+f"(d[59]), "+f"(d[60]), "+f"(d[61]), "+f"(d[62]), "+f"(d[63]), "+f"(d[64]), "+f"(d[65]), "+f"(d[66]), "+f"(d[67]), "+f"(d[68]), "+f"(d[69]), "+f"(d[70]), "+f"(d[71]), "+f"(d[72]), "+f"(d[73]), "+f"(d[74]), "+f"(d[75]), "+f"(d[76]), "+f"(d[77]), "+f"(d[78]), "+f"(d[79]), "+f"(d[80]), "+f"(d[81]), "+f"(d[82]), "+f"(d[83]), "+f"(d[84]), "+f"(d[85]), "+f"(d[86]), "+f"(d[87]), "+f"(d[88]), "+f"(d[89]), "+f"(d[90]), "+f"(d[91]), "+f"(d[92]), "+f"(d[93]), "+f"(d[94]), "+f"(d[95])
        : "l"(descA), "l"(descB));
}

constexpr int K1_LEAD = 1;
constexpr int K1_THREADS = 384;
constexpr int K1_STAGE = 16384 + 40960;
constexpr int K1_SMEM = 4 * K1_STAGE + 1024 + 256;

__global__ void __launch_bounds__(K1_THREADS, 1)
k1_proj(const __grid_constant__ CUtensorMap tmX, const __grid_constant__ CUtensorMap tmWq,
        const __grid_constant__ CUtensorMap tmWqkv, const __grid_constant__ CUtensorMap tmQo,
        const __grid_constant__ CUtensorMap tmQKVo, const __nv_bfloat16* __restrict__ Wk,
        const __nv_bfloat16* __restrict__ Wv, const __nv_bfloat16* __restrict__ gate_w) {
    extern __shared__ uint8_t smem_raw[];
    const uint32_t sbase = (smem_u32(smem_raw) + 1023u) & ~1023u;
    uint8_t* sgen = smem_raw + (sbase - smem_u32(smem_raw));
    const uint32_t bars = sbase + 4 * K1_STAGE;
    const int tid = threadIdx.x, warp = tid >> 5, lane = tid & 31;
    const bool is_kv = blockIdx.x >= 128;
    const int j = (blockIdx.x >> 1) & 7;
    const int row0 = ((blockIdx.x >> 4) * 2 + (blockIdx.x & 1)) * 128;
    const int kvb = blockIdx.x - 128;
    constexpr uint32_t W_OFF = 163840;

    if (tid == 0) TSTAMP(0, 0);
    uint4 wk[7], wv[7];
    uint32_t gw[3];
    if (is_kv && tid < 256) {
#pragma unroll
        for (int i = 0; i < 7; i++) {
            const int ch = min(tid + i * 256, 1599);
            wk[i] = __ldg((const uint4*)Wk + ch);
            wv[i] = __ldg((const uint4*)Wv + ch);
        }
#pragma unroll
        for (int i = 0; i < 3; i++) gw[i] = __ldg((const uint16_t*)gate_w + min(tid + i * 256, 639));
    }
    if (tid == 256) {
        for (int s = 0; s < 10; s++) {
            mbar_init(bars + s * 8, 1);
            mbar_init(bars + 128 + s * 8, 8);
        }
        fence_barrier_init();
        fence_proxy_async();
    }
    if (tid == 288) {
        prefetch_tmap(&tmX);
        prefetch_tmap((j < 2) ? &tmWq : &tmWqkv);
        prefetch_tmap((j < 2) ? &tmQo : &tmQKVo);
    }
    __syncthreads();
    griddep_launch();

    if (warp >= 8) {
        asm volatile("setmaxnreg.dec.sync.aligned.u32 40;");
        if (tid == 256) {
            if (!is_kv) {
                const CUtensorMap* tw = (j < 2) ? &tmWq : &tmWqkv;
                const int slab0 = (j < 2) ? j * 5 : (j - 2) * 5;
                for (int kb = 0; kb < 10; kb++) {
                    const int s = kb & 3;
                    const uint32_t st = sbase + s * K1_STAGE;
                    if (kb == 2) mbar_wait(bars, 0);
                    if (kb >= 4) mbar_wait(bars + 128 + s * 8, ((kb >> 2) - 1) & 1);
                    mbar_expect_tx(bars + s * 8, K1_STAGE);
                    tma_2d(st, &tmX, kb * 64, row0, bars + s * 8);
                    tma_3d(st + 16384, tw, 0, kb * 64, slab0, bars + s * 8);
                }
            } else {
                for (int rb = 0; rb < 4; rb++) {
                    for (int s = 0; s < 10; s++) {
                        if (rb >= 1) mbar_wait(bars + 128 + s * 8, (rb - 1) & 1);
                        mbar_expect_tx(bars + s * 8, 16384);
                        tma_2d(sbase + s * 16384, &tmX, s * 64, kvb * 512 + rb * 128, bars + s * 8);
                    }
                }
            }
        }
    } else {
        asm volatile("setmaxnreg.inc.sync.aligned.u32 232;");
        if (tid == 0) TSTAMP(0, 1);
        const int wg = warp >> 2;
        if (!is_kv) {
            const uint64_t dA0 = make_desc(sbase + wg * 8192, 16, 1024, 1);
            const uint64_t dB0 = make_desc(sbase + 16384, 8192, 1024, 1);
            {
                float acc0[96], acc1[64];
#pragma unroll
                for (int i = 0; i < 96; i++) acc0[i] = 0.f;
#pragma unroll
                for (int i = 0; i < 64; i++) acc1[i] = 0.f;
                fence_regs(acc0);
                fence_regs(acc1);
                if (wg == 1) named_bar_sync(4, 256);
#pragma unroll 1
                for (int kb = 0; kb < 10; kb++) {
                    const int s = kb & 3;
                    mbar_wait_warp(bars + s * 8, (kb >> 2) & 1);
                    if (tid == 0 && kb < 10) TSTAMP(0, 2 + kb);
                    const uint64_t so = (uint64_t)(s * (K1_STAGE >> 4));
                    wg_fence();
#pragma unroll
                    for (int kk = 0; kk < 4; kk++) {
                        const uint64_t da = dA0 + so + (uint64_t)(kk * 2);
                        const uint64_t db = dB0 + so + (uint64_t)(kk * 128);
                        wgmma_n192_ss_tb(acc0, da, db);
                        wgmma_n128_ss_tb(acc1, da, db + (uint64_t)((3 * 8192) >> 4));
                    }
                    wg_commit();
                    wg_wait<1>();
                    if (wg == 0 && kb == K1_LEAD - 1) asm volatile("bar.arrive 4, 256;" ::: "memory");
                    if (kb >= 1 && kb <= 8 && lane == 0) mbar_arrive(bars + 128 + ((kb - 1) & 3) * 8);
                }
                wg_wait<0>();
                fence_regs(acc0);
                fence_regs(acc1);
                mbar_wait_warp(bars + 128 + (2 + wg) * 8, 1);
                if (tid == 0) TSTAMP(0, 12);
                const uint32_t stg = sbase + (2 + wg) * K1_STAGE + (warp & 3) * 10240;
                const int srow = (lane & 7) + ((lane >> 3) & 1) * 8;
                const uint32_t sa = stg + srow * 128;
                const int hi = lane >> 4, sw = lane & 7;
#pragma unroll
                for (int jb = 0; jb < 40; jb += 2) {
                    uint32_t r0, r1, r2, r3;
                    if (jb < 24) {
                        r0 = pack_bf16(acc0[4 * jb], acc0[4 * jb + 1]); r1 = pack_bf16(acc0[4 * jb + 2], acc0[4 * jb + 3]);
                        r2 = pack_bf16(acc0[4 * jb + 4], acc0[4 * jb + 5]); r3 = pack_bf16(acc0[4 * jb + 6], acc0[4 * jb + 7]);
                    } else {
                        const int b = 4 * (jb - 24);
                        r0 = pack_bf16(acc1[b], acc1[b + 1]); r1 = pack_bf16(acc1[b + 2], acc1[b + 3]);
                        r2 = pack_bf16(acc1[b + 4], acc1[b + 5]); r3 = pack_bf16(acc1[b + 6], acc1[b + 7]);
                    }
                    const uint32_t addr = sa + (jb >> 3) * 2048 + ((((jb & 7) + hi) ^ sw) << 4);
                    asm volatile("stmatrix.sync.aligned.m8n8.x4.shared.b16 [%0], {%1, %2, %3, %4};"
                                 ::"r"(addr), "r"(r0), "r"(r1), "r"(r2), "r"(r3) : "memory");
                }
                fence_proxy_async();
                __syncwarp();
                if (lane < 5) {
                    const CUtensorMap* to = (j < 2) ? &tmQo : &tmQKVo;
                    const int col = ((j < 2) ? j : j - 2) * 320 + lane * 64;
                    asm volatile("cp.async.bulk.tensor.2d.global.shared::cta.bulk_group [%0, {%2, %3}], [%1];"
                                 ::"l"(to), "r"(stg + lane * 2048), "r"(col), "r"(row0 + warp * 16) : "memory");
                    asm volatile("cp.async.bulk.commit_group;" ::: "memory");
                    asm volatile("cp.async.bulk.wait_group 0;" ::: "memory");
                }
                __syncwarp();
            }
        } else {
            {
#pragma unroll
                for (int i = 0; i < 7; i++) {
                    const int ch = min(tid + i * 256, 1599);
#pragma unroll
                    for (int hf = 0; hf < 2; hf++) {
                        const int q4 = ch * 2 + hf;
                        const int k = q4 / 5, pc = q4 % 5;
                        uint8_t* w = sgen + W_OFF + (k >> 3) * 768 + (k & 7) * 16 + (pc >> 1) * 128 + (pc & 1) * 8;
                        *(uint2*)(w) = hf ? make_uint2(wk[i].z, wk[i].w) : make_uint2(wk[i].x, wk[i].y);
                        *(uint2*)(w + 384) = hf ? make_uint2(wv[i].z, wv[i].w) : make_uint2(wv[i].x, wv[i].y);
                    }
                }
#pragma unroll
                for (int i = 0; i < 3; i++) {
                    const int k = min(tid + i * 256, 639);
                    uint8_t* w = sgen + W_OFF + (k >> 3) * 768 + (k & 7) * 16 + 256 + 8;
                    *(uint2*)(w) = make_uint2(0u, 0u);
                    *(uint2*)(w + 384) = make_uint2(gw[i], 0u);
                }
            }
            fence_proxy_async();
            named_bar_sync(1, 256);
            if (tid == 0) TSTAMP(0, 2);
            const uint64_t dA0 = make_desc(sbase + wg * 8192, 16, 1024, 1);
            const uint64_t dW0 = make_desc(sbase + W_OFF, 768, 128, 0);
            const int c = lane & 3;
#pragma unroll 1
            for (int rb = 0; rb < 4; rb++) {
                float acc[24];
#pragma unroll
                for (int i = 0; i < 24; i++) acc[i] = 0.f;
                fence_regs(acc);
#pragma unroll 1
                for (int kb = 0; kb < 10; kb += 2) {
                    mbar_wait_warp(bars + kb * 8, rb & 1);
                    mbar_wait_warp(bars + kb * 8 + 8, rb & 1);
                    wg_fence();
#pragma unroll
                    for (int kk = 0; kk < 8; kk++)
                        wgmma_n48_ss_tb(acc, dA0 + (uint64_t)((kb + (kk >> 2)) * 1024 + (kk & 3) * 2), dW0 + (uint64_t)((kb * 8 + kk * 2) * 48));
                    wg_commit();
                    wg_wait<1>();
                    if (kb >= 2 && lane < 2) mbar_arrive(bars + 128 + (kb - 2 + lane) * 8);
                }
                wg_wait<0>();
                if (lane < 2) mbar_arrive(bars + 128 + (8 + lane) * 8);
                fence_regs(acc);
                if (tid == 0) TSTAMP(0, 3 + rb);
                float nmax = 0.f;
#pragma unroll
                for (int hh = 0; hh < 2; hh++) {
                    const int key = kvb * 512 + rb * 128 + warp * 16 + hh * 8 + (lane >> 2);
                    const int kg = key >> 3;
                    const bool sc = (SC_MASK >> (kg & 15)) & 1;
                    uint32_t* img = g_KV + ((kg >> 4) * 12288 + (kg & 15) * 128 + (key & 7) * 16 + c * 4) / 4;
                    uint32_t* imv = g_KV + ((kg >> 4) * 12288 + 6144 + (kg & 15) * 384 + (key & 7) * 16 + c * 4) / 4;
                    const uint32_t k0 = pack_bf16(acc[0 + 2 * hh] * K_SCALE, acc[1 + 2 * hh] * K_SCALE);
                    const uint32_t k1 = pack_bf16(acc[4 + 2 * hh] * K_SCALE, acc[5 + 2 * hh] * K_SCALE);
                    uint32_t k2 = pack_bf16(acc[8 + 2 * hh] * K_SCALE, acc[9 + 2 * hh] * K_SCALE);
                    float n2 = bf_lo(k0) * bf_lo(k0) + bf_hi(k0) * bf_hi(k0) + bf_lo(k1) * bf_lo(k1) + bf_hi(k1) * bf_hi(k1);
                    if (c < 2) n2 += bf_lo(k2) * bf_lo(k2) + bf_hi(k2) * bf_hi(k2);
                    if (c == 2) k2 = sc ? 0x438042E4u : 0x3F16C150u;
                    if (c == 3) k2 = sc ? 0x00003B80u : 0x000039AAu;
                    img[0] = k0;
                    img[512] = k1;
                    img[1024] = k2;
                    const uint32_t sgn = sc ? 0x80008000u : 0u;
                    const uint32_t v0 = pack_bf16(acc[12 + 2 * hh], acc[13 + 2 * hh]) ^ sgn;
                    const uint32_t v1 = pack_bf16(acc[16 + 2 * hh], acc[17 + 2 * hh]) ^ sgn;
                    uint32_t v2 = pack_bf16(acc[20 + 2 * hh], acc[21 + 2 * hh]) ^ sgn;
                    if (c == 2) {
                        v2 = sc ? 0x0000BF80u : 0x00003F80u;
                        g_gate[key] = 1.f / (1.f + __expf(-acc[20 + 2 * hh]));
                    }
                    if (c == 3) v2 = 0u;
                    imv[0] = v0;
                    imv[32] = v1;
                    imv[64] = v2;
                    n2 += __shfl_xor_sync(0xffffffffu, n2, 1);
                    n2 += __shfl_xor_sync(0xffffffffu, n2, 2);
                    nmax = (n2 > nmax || n2 != n2) ? n2 : nmax;
                }
#pragma unroll
                for (int o = 4; o < 32; o <<= 1) {
                    const float t = __shfl_xor_sync(0xffffffffu, nmax, o);
                    nmax = (t > nmax || t != t) ? t : nmax;
                }
                if (lane == 0) g_kmax[(kvb * 4 + rb) * 8 + warp] = nmax;
            }
        }
        if (tid == 0) TSTAMP(0, 13);
    }
}

constexpr int K2_THREADS = 512;
constexpr int K2_BARS = 225280;
constexpr int K2_SMEM = K2_BARS + 1024 + 256;
constexpr int TN = 64;
constexpr int NT = SEQ / TN;
constexpr uint64_t CHD = 12288 >> 4;
constexpr uint64_t DK0 = (uint64_t)(2048 >> 4) << 16;
constexpr uint64_t DK1 = 4096 >> 4;
constexpr uint64_t DV = ((uint64_t)(384 >> 4) << 16) + (6144 >> 4);

__device__ __forceinline__ uint32_t sc_pair(float w0, float w1, uint32_t cM) {
    uint32_t X, M, E, P;
    asm("prmt.b32 %0, %1, %2, 0x6521;" : "=r"(X) : "r"(__float_as_uint(w0)), "r"(__float_as_uint(w1)));
    asm("lop3.b32 %0, %1, 0x007F007F, %2, 0xEA;" : "=r"(M) : "r"(X), "r"(cM));
    E = X & 0xFF80FF80u;
    asm("fma.rn.bf16x2 %0, %1, %2, %3;" : "=r"(P) : "r"(X), "r"(M), "r"(E));
    return P;
}
template <int BLK0>
__device__ __forceinline__ void do_exp(const float (&s)[32], uint32_t (&p)[16], uint32_t cM) {
#pragma unroll
    for (int j = 0; j < 8; j++) {
        if ((SC_MASK >> (BLK0 + j)) & 1) {
            p[2 * j + 0] = sc_pair(s[4 * j + 0], s[4 * j + 1], cM);
            p[2 * j + 1] = sc_pair(s[4 * j + 2], s[4 * j + 3], cM);
        } else {
            const float e0 = ex2_mufu(s[4 * j + 0]), e1 = ex2_mufu(s[4 * j + 1]);
            const float e2 = ex2_mufu(s[4 * j + 2]), e3 = ex2_mufu(s[4 * j + 3]);
            p[2 * j + 0] = pack_bf16(e0, e1);
            p[2 * j + 1] = pack_bf16(e2, e3);
        }
    }
}
template <int H>
__device__ __forceinline__ void mma_qk(float (&s)[32], const uint32_t (&q)[6], uint64_t d) {
    wgmma_n64_rs_z(s, q[0], q[1], q[2], q[3], d + DK0 + H * 64);
    wgmma_n64_rs(s, q[4], q[5], 0u, 0u, d + DK1 + H * 64);
}
template <int H>
__device__ __forceinline__ void mma_pv(float (&o)[12], const uint32_t (&p)[16], uint64_t d) {
#pragma unroll
    for (int kk = 0; kk < 4; kk++)
        wgmma_n24_rs_tb(o, p[4 * kk + 0], p[4 * kk + 1], p[4 * kk + 2], p[4 * kk + 3], d + DV + H * 192 + kk * 48);
}

__device__ __forceinline__ void attn_safe(float (&o)[12], const uint32_t (&q)[6], uint64_t d0, uint32_t bars) {
    float s[32];
    uint32_t p[16];
    float m0 = -INFINITY, m1 = -INFINITY;
#pragma unroll 1
    for (int t = 0; t < NT; t++) {
        mbar_wait_warp(bars + (t >> 1) * 8, 0);
        wg_fence();
        mma_qk<0>(s, q, d0 + (t >> 1) * CHD + (t & 1) * 64);
        wg_commit();
        wg_wait<0>();
        fence_regs(s);
#pragma unroll
        for (int j = 0; j < 8; j++) {
            m0 = fmaxf(m0, fmaxf(s[4 * j], s[4 * j + 1]));
            m1 = fmaxf(m1, fmaxf(s[4 * j + 2], s[4 * j + 3]));
        }
    }
    m0 = fmaxf(m0, __shfl_xor_sync(0xffffffffu, m0, 1));
    m0 = fmaxf(m0, __shfl_xor_sync(0xffffffffu, m0, 2));
    m1 = fmaxf(m1, __shfl_xor_sync(0xffffffffu, m1, 1));
    m1 = fmaxf(m1, __shfl_xor_sync(0xffffffffu, m1, 2));
#pragma unroll
    for (int i = 0; i < 12; i++) o[i] = 0.f;
    fence_regs(o);
#pragma unroll 1
    for (int t = 0; t < NT; t++) {
        wg_fence();
        mma_qk<0>(s, q, d0 + (t >> 1) * CHD + (t & 1) * 64);
        wg_commit();
        wg_wait<0>();
        fence_regs(s);
        const uint32_t msk = SC_MASK >> ((t & 1) * 8);
#pragma unroll
        for (int j = 0; j < 8; j++) {
            const uint32_t sgn = ((msk >> j) & 1) ? 0x80008000u : 0u;
            p[2 * j + 0] = pack_bf16(ex2_mufu(s[4 * j + 0] - m0), ex2_mufu(s[4 * j + 1] - m0)) ^ sgn;
            p[2 * j + 1] = pack_bf16(ex2_mufu(s[4 * j + 2] - m1), ex2_mufu(s[4 * j + 3] - m1)) ^ sgn;
        }
        fence_regs(p);
        wg_fence();
        mma_pv<0>(o, p, d0 + (t >> 1) * CHD + (t & 1) * 192);
        wg_commit();
        wg_wait<0>();
        fence_regs(o);
    }
}

constexpr int LA_PITCH = 352;
constexpr int LA_GRP = 80 * LA_PITCH;
constexpr int LA_MAIN_OFF = 98304;
__device__ __forceinline__ void mma16816(float (&d)[4], uint32_t a0, uint32_t a1, uint32_t a2, uint32_t a3, uint32_t b0,
                                         uint32_t b1) {
    asm volatile("mma.sync.aligned.m16n8k16.row.col.f32.bf16.bf16.f32 {%0,%1,%2,%3}, {%4,%5,%6,%7}, {%8,%9}, {%0,%1,%2,%3};"
                 : "+f"(d[0]), "+f"(d[1]), "+f"(d[2]), "+f"(d[3])
                 : "r"(a0), "r"(a1), "r"(a2), "r"(a3), "r"(b0), "r"(b1));
}
__device__ __forceinline__ void mma1688(float (&d)[4], uint32_t a0, uint32_t a1, uint32_t b0) {
    asm volatile("mma.sync.aligned.m16n8k8.row.col.f32.bf16.bf16.f32 {%0,%1,%2,%3}, {%4,%5}, {%6}, {%0,%1,%2,%3};"
                 : "+f"(d[0]), "+f"(d[1]), "+f"(d[2]), "+f"(d[3])
                 : "r"(a0), "r"(a1), "r"(b0));
}
__device__ __forceinline__ uint32_t movm_t(uint32_t a) {
    uint32_t d;
    asm volatile("movmatrix.sync.aligned.m8n8.trans.b16 %0, %1;" : "=r"(d) : "r"(a));
    return d;
}
template <int NHD>
__device__ __forceinline__ void local_attn(uint8_t* sgrp, int p0, int h0) {
    const int lane = threadIdx.x & 31, g = lane >> 2, c = lane & 3, e = g & 1;
    const uint8_t* kb = sgrp + g * LA_PITCH + (h0 & 7) * 40;
    uint8_t* qb = sgrp + (64 + g) * LA_PITCH + (h0 & 7) * 40;
    const int o8 = c * 8, o4 = 32 + (c & 1) * 4;
    const bool lo2 = c < 2, odd = c & 1;
    float x0[NHD][4], x1[NHD][4];
#pragma unroll
    for (int u = 0; u < NHD; u++) {
        const uint8_t* q = qb + u * 40;
        const uint2 qa = *(const uint2*)(q + o8), qc = *(const uint2*)(q + 8 * LA_PITCH + o8);
        const uint2 qe = *(const uint2*)(q + 32), qf = *(const uint2*)(q + 8 * LA_PITCH + 32);
        const uint32_t a4 = lo2 ? (odd ? qe.y : qe.x) : 0u, a5 = lo2 ? (odd ? qf.y : qf.x) : 0u;
#pragma unroll
        for (int nb = 0; nb < 4; nb++) {
            const uint8_t* kr = kb + u * 40 + 8 * nb * LA_PITCH;
            const uint2 b = *(const uint2*)(kr + o8);
            const uint2 be = *(const uint2*)(kr + 32);
            const uint32_t b2 = odd ? be.y : be.x;
            float sacc[4] = {0.f, 0.f, 0.f, 0.f};
            mma16816(sacc, qa.x, qc.x, qa.y, qc.y, b.x, b.y);
            mma1688(sacc, a4, a5, b2);
            const int j = 8 * nb + 2 * c + e;
            const bool inb = (p0 - 16 + j) >= 0;
            const bool v0 = inb && (j >= g + 2) && (j <= g + 16);
            const bool v1 = inb && (j >= g + 10) && (j <= g + 24);
            x0[u][nb] = v0 ? (e ? sacc[1] : sacc[0]) : -INFINITY;
            x1[u][nb] = v1 ? (e ? sacc[3] : sacc[2]) : -INFINITY;
        }
    }
    float m0[NHD], m1[NHD];
#pragma unroll
    for (int u = 0; u < NHD; u++) {
        m0[u] = fmaxf(fmaxf(x0[u][0], x0[u][1]), fmaxf(x0[u][2], x0[u][3]));
        m1[u] = fmaxf(fmaxf(x1[u][0], x1[u][1]), fmaxf(x1[u][2], x1[u][3]));
    }
#pragma unroll
    for (int sh = 1; sh <= 2; sh <<= 1) {
#pragma unroll
        for (int u = 0; u < NHD; u++) {
            m0[u] = fmaxf(m0[u], __shfl_xor_sync(0xffffffffu, m0[u], sh));
            m1[u] = fmaxf(m1[u], __shfl_xor_sync(0xffffffffu, m1[u], sh));
        }
    }
#pragma unroll
    for (int u = 0; u < NHD; u++) {
        uint32_t pa[4][2];
#pragma unroll
        for (int nb = 0; nb < 4; nb++) {
            pa[nb][0] = pack_bf16(ex2_mufu(fmaf(x0[u][nb], K_SCALE, -K_SCALE * m0[u])), 0.f) << (16 * e);
            pa[nb][1] = pack_bf16(ex2_mufu(fmaf(x1[u][nb], K_SCALE, -K_SCALE * m1[u])), 0.f) << (16 * e);
        }
        float o[3][4];
#pragma unroll
        for (int nd = 0; nd < 3; nd++) { o[nd][0] = 0.f; o[nd][1] = 0.f; o[nd][2] = 0.f; o[nd][3] = 0.f; }
#pragma unroll
        for (int ks = 0; ks < 2; ks++) {
            const uint8_t* v0 = kb + u * 40 + (32 + 16 * ks) * LA_PITCH;
            const uint8_t* v1 = v0 + 8 * LA_PITCH;
            const uint2 s0 = *(const uint2*)(v0 + o8), s1 = *(const uint2*)(v1 + o8);
            const uint2 te = *(const uint2*)(v0 + 32), tf = *(const uint2*)(v1 + 32);
            uint32_t t0 = odd ? te.y : te.x, t1 = odd ? tf.y : tf.x;
            const uint32_t fill = (c == 2) ? 0x00003F80u : 0u;
            t0 = lo2 ? t0 : fill;
            t1 = lo2 ? t1 : fill;
            mma16816(o[0], pa[2 * ks][0], pa[2 * ks][1], pa[2 * ks + 1][0], pa[2 * ks + 1][1], movm_t(s0.x), movm_t(s1.x));
            mma16816(o[1], pa[2 * ks][0], pa[2 * ks][1], pa[2 * ks + 1][0], pa[2 * ks + 1][1], movm_t(s0.y), movm_t(s1.y));
            mma16816(o[2], pa[2 * ks][0], pa[2 * ks][1], pa[2 * ks + 1][0], pa[2 * ks + 1][1], movm_t(t0), movm_t(t1));
        }
        const float i0 = __fdividef(1.f, __shfl_sync(0xffffffffu, o[2][0], (lane & ~3) | 2));
        const float i1 = __fdividef(1.f, __shfl_sync(0xffffffffu, o[2][2], (lane & ~3) | 2));
        uint8_t* q = qb + u * 40;
        *(uint2*)(q + o8) = make_uint2(pack_bf16(o[0][0] * i0, o[0][1] * i0), pack_bf16(o[1][0] * i0, o[1][1] * i0));
        *(uint2*)(q + 8 * LA_PITCH + o8) = make_uint2(pack_bf16(o[0][2] * i1, o[0][3] * i1), pack_bf16(o[1][2] * i1, o[1][3] * i1));
        if (lo2) {
            *(uint32_t*)(q + o4) = pack_bf16(o[2][0] * i0, o[2][1] * i0);
            *(uint32_t*)(q + 8 * LA_PITCH + o4) = pack_bf16(o[2][2] * i1, o[2][3] * i1);
        }
    }
}
__device__ __forceinline__ void la_store(const uint8_t* sgrp, int p0, int grp, int t, int nthr) {
#pragma unroll 1
    for (int i = t; i < 320; i += nthr) {
        const int row = i / 20, ch = i % 20;
        *(uint4*)(g_O + (size_t)(p0 + row) * (2 * DM) + DM + grp * 160 + ch * 8) = *(const uint4*)(sgrp + (64 + row) * LA_PITCH + ch * 16);
    }
}

__device__ __forceinline__ void la_copy(int part, uint32_t sgrp, const CUtensorMap* tkv, const CUtensorMap* tq, int p0, int grp,
                                        uint32_t bar) {
    if (part < 2) tma_2d(sgrp + part * 32 * LA_PITCH, tkv, (1 + part) * DM + grp * 160, p0 - 16, bar);
    else tma_2d(sgrp + 64 * LA_PITCH, tq, grp * 160, p0, bar);
}

__device__ __forceinline__ int attn_row0(int mt) {
    return (blockIdx.x * 8 + mt) * 64 + ((threadIdx.x >> 5) & 3) * 16 + ((threadIdx.x & 31) >> 2);
}
__device__ __forceinline__ void load_q(uint32_t (&q)[6], int mt) {
    const int c = threadIdx.x & 3;
    const uint32_t* q0 = (const uint32_t*)(g_Q + (size_t)attn_row0(mt) * DH);
    const uint32_t* q1 = q0 + 8 * DH / 2;
    q[0] = q0[c]; q[1] = q1[c]; q[2] = q0[4 + c]; q[3] = q1[4 + c];
    q[4] = (c < 2) ? q0[8 + c] : 0u;
    q[5] = (c < 2) ? q1[8 + c] : 0u;
}
__device__ __forceinline__ void store_o(const float (&o)[12], int mt) {
    const int lane = threadIdx.x & 31, c = lane & 3;
    const int row0 = attn_row0(mt);
    const float l0 = __shfl_sync(0xffffffffu, o[8], (lane & ~3) | 2);
    const float l1 = __shfl_sync(0xffffffffu, o[10], (lane & ~3) | 2);
    const float r0 = 1.f / l0, r1 = 1.f / l1;
    uint32_t* o0 = (uint32_t*)(g_O + (size_t)(row0 >> 5) * (2 * DM) + (row0 & 31) * DH);
    uint32_t* o1 = o0 + 8 * DH / 2;
    o0[c] = pack_bf16(o[0] * r0, o[1] * r0);
    o1[c] = pack_bf16(o[2] * r1, o[3] * r1);
    o0[4 + c] = pack_bf16(o[4] * r0, o[5] * r0);
    o1[4 + c] = pack_bf16(o[6] * r1, o[7] * r1);
    if (c < 2) {
        o0[8 + c] = pack_bf16(o[8] * r0, o[9] * r0);
        o1[8 + c] = pack_bf16(o[10] * r1, o[11] * r1);
    }
}

__device__ __forceinline__ bool prep_q(uint32_t (&q)[6], float kmax) {
    const int c = threadIdx.x & 3;
    float n0 = bf_lo(q[0]) * bf_lo(q[0]) + bf_hi(q[0]) * bf_hi(q[0]) + bf_lo(q[2]) * bf_lo(q[2]) + bf_hi(q[2]) * bf_hi(q[2]) +
               bf_lo(q[4]) * bf_lo(q[4]) + bf_hi(q[4]) * bf_hi(q[4]);
    float n1 = bf_lo(q[1]) * bf_lo(q[1]) + bf_hi(q[1]) * bf_hi(q[1]) + bf_lo(q[3]) * bf_lo(q[3]) + bf_hi(q[3]) * bf_hi(q[3]) +
               bf_lo(q[5]) * bf_lo(q[5]) + bf_hi(q[5]) * bf_hi(q[5]);
    n0 += __shfl_xor_sync(0xffffffffu, n0, 1);
    n1 += __shfl_xor_sync(0xffffffffu, n1, 1);
    n0 += __shfl_xor_sync(0xffffffffu, n0, 2);
    n1 += __shfl_xor_sync(0xffffffffu, n1, 2);
    const bool ok = (n0 * kmax <= 12544.f) && (n1 * kmax <= 12544.f);
    if (!ok) { q[0] = 0u; q[1] = 0u; q[2] = 0u; q[3] = 0u; q[4] = 0u; q[5] = 0u; }
    if (c == 2) { q[4] = 0x3F803F80u; q[5] = 0x3F803F80u; }
    if (c == 3) { q[4] = 0x00003F80u; q[5] = 0x00003F80u; }
    return ok;
}

constexpr int K2_PART_OFF = KV_BYTES;
constexpr int K2_FLAG_OFF = K2_BARS + 192;

__global__ void __launch_bounds__(K2_THREADS, 1)
k2_attn(const __grid_constant__ CUtensorMap tmLkv, const __grid_constant__ CUtensorMap tmLq) {
    extern __shared__ uint8_t smem_raw[];
    const uint32_t sbase = (smem_u32(smem_raw) + 1023u) & ~1023u;
    const uint32_t bars = sbase + K2_BARS;
    const int tid = threadIdx.x, lane = tid & 31;
    const int wg = __shfl_sync(0xffffffffu, tid >> 7, 0);
    if (tid == 0) TSTAMP(1, 0);
    uint8_t* sgen = smem_raw + (sbase - smem_u32(smem_raw));
    const int p0 = blockIdx.x * 16;
    const bool extra = (blockIdx.x & 1) == 1;
    if (tid == 0) {
        for (int c = 0; c < 17; c++) mbar_init(bars + c * 8, 1);
        mbar_init(bars + 136, 16);
        *(volatile uint32_t*)(sgen + K2_FLAG_OFF) = 0u;
        fence_barrier_init();
        fence_proxy_async();
        mbar_expect_tx(bars + 128, (extra ? 3 : 2) * LA_GRP);
        prefetch_tmap(&tmLkv);
        prefetch_tmap(&tmLq);
    }
    __syncthreads();
    griddep_wait();
    if (tid == 0) TSTAMP(1, 1);
    if (blockIdx.x >= 128) {
        griddep_launch();
        const int pbase = (blockIdx.x - 128) * 512 + wg * 128;
        const int t128 = tid & 127;
#pragma unroll 1
        for (int r = -2; r < 12; r++) {
            const int bsel = wg * 2 + (r & 1);
            uint8_t* buf = sgen + bsel * LA_GRP;
            const int tq = (r + 3) / 3 - 1, tr = r - 3 * tq, nq = (r + 2) / 3, nr = r + 2 - 3 * nq;
            const int pc = pbase + tq * 32 + (tr >> 1) * 16, gc = 3 - (tr & 1);
            const int pn = pbase + nq * 32 + (nr >> 1) * 16, gn = 3 - (nr & 1);
            const bool refill = r + 2 < 12;
            if (r >= 0) {
                mbar_wait_warp(bars + bsel * 8, (r >> 1) & 1);
                local_attn<2>(buf, pc, gc * 8 + (t128 >> 5) * 2);
                named_bar_sync(1 + wg, 128);
            }
            if (t128 < 96) {
                if (r >= 0) la_store(buf, pc, gc, t128, 96);
            } else if (refill && t128 < 98) {
                if (t128 == 96) mbar_expect_tx(bars + bsel * 8, LA_GRP);
                fence_proxy_async();
                la_copy(t128 - 96, sbase + bsel * LA_GRP, &tmLkv, &tmLq, pn, gn, bars + bsel * 8);
            }
            __syncwarp();
            named_bar_sync(1 + wg, 128);
            if (refill && t128 == 64) {
                fence_proxy_async();
                la_copy(2, sbase + bsel * LA_GRP, &tmLkv, &tmLq, pn, gn, bars + bsel * 8);
            }
            __syncwarp();
        }
        if (tid == 0) TSTAMP(1, 2);
        return;
    }
    uint32_t q[6], qo[6];
    load_q(q, 2 * wg);
    load_q(qo, 2 * wg + 1);
    const float4 km4 = __ldcg((const float4*)(g_kmax + lane * 4));
    {
        const int wi = tid >> 5;
        if (lane == 0 && wi < 2) {
            mbar_expect_tx(bars + wi * 8, 12288);
            bulk_g2s(sbase + wi * 12288, (const uint8_t*)g_KV + wi * 12288, 12288, bars + wi * 8);
        }
        if (lane < 3 && wi >= 2 && wi < (extra ? 5 : 4)) la_copy(lane, sbase + LA_MAIN_OFF + (wi - 2) * LA_GRP, &tmLkv, &tmLq, p0, wi - 2, bars + 128);
        if (lane == 0 && wi >= 2 && wi < 8) {
            mbar_expect_tx(bars + wi * 8, 12288);
            bulk_g2s(sbase + wi * 12288, (const uint8_t*)g_KV + wi * 12288, 12288, bars + wi * 8);
        }
    }
    griddep_launch();
    float kmax;
    {
        uint32_t u = max(max(__float_as_uint(km4.x), __float_as_uint(km4.y)), max(__float_as_uint(km4.z), __float_as_uint(km4.w)));
        u = __reduce_max_sync(0xffffffffu, u);
        kmax = __uint_as_float(u);
    }

    const uint64_t d0 = make_desc(sbase, 0, 128, 0);
    const int c = lane & 3;
    uint32_t cM = 0x3F003F00u;
    asm volatile("" : "+r"(cM));
    {
        const bool okA = prep_q(q, kmax), okB = prep_q(qo, kmax);
        if (!(okA && okB)) atomicOr((uint32_t*)(sgen + K2_FLAG_OFF), (okA ? 0u : 1u << (2 * wg)) | (okB ? 0u : 2u << (2 * wg)));
    }
    float o[12];
#pragma unroll 1
    for (int un = 0; un < 3; un++) {
        if (un == (wg >> 1)) {
            const int npass = (extra && un == 1) ? 3 : 2;
#pragma unroll 1
            for (int pass = 1; pass < npass; pass++) {
                mbar_wait_warp(bars + 128, 0);
                if ((tid & 255) == 0 && pass < 2) TSTAMP(1, 12 + pass + un);
                const int grp = (pass == 2) ? 2 : un;
                local_attn<1>(sgen + LA_MAIN_OFF + grp * LA_GRP, p0, (tid >> 5) & 7);
                named_bar_sync(1 + un, 256);
                la_store(sgen + LA_MAIN_OFF + grp * LA_GRP, p0, grp, tid & 255, 256);
            }
            __syncwarp();
            if (lane == 0) {
                mbar_arrive(bars + 136);
                if (un) {
                    mbar_wait(bars + 136, 0);
                    fence_proxy_async();
                    const int cc = tid >> 5;
                    mbar_expect_tx(bars + cc * 8, 12288);
                    bulk_g2s(sbase + cc * 12288, (const uint8_t*)g_KV + cc * 12288, 12288, bars + cc * 8);
                }
            }
            __syncwarp();
        }
        const int mt = 2 * wg + (un & 1);
        if (un != 0) {
#pragma unroll
            for (int i = 0; i < 6; i++) { const uint32_t t = q[i]; q[i] = qo[i]; qo[i] = t; }
        }
#pragma unroll
        for (int i = 0; i < 12; i++) o[i] = 0.f;
        fence_regs(o);
        float s[32];
        uint32_t p0r[16], p1r[16];
        const uint32_t cb = bars + ((un == 2) ? 64 : 0);
        uint64_t dc = d0 + ((un == 2) ? 8 * CHD : 0);
        const int tend = (un == 1) ? 30 : 14;
        const int twait = (un == 0) ? 0 : 14;
        mbar_wait_warp(cb, 0);
        if ((tid & 255) == 0 && un == 0) TSTAMP(1, 2 + (tid >> 8) * 5);
        wg_fence();
        mma_qk<0>(s, q, dc);
        wg_commit();
        wg_wait<0>();
        fence_regs(s);
        do_exp<0>(s, p0r, cM);
        fence_regs(p0r);
#pragma unroll 1
        for (int t = 0; t < tend; t += 2) {
            wg_fence();
            mma_qk<1>(s, q, dc);
            wg_commit();
            mma_pv<0>(o, p0r, dc);
            wg_commit();
            wg_wait<1>();
            fence_regs(s);
            do_exp<8>(s, p1r, cM);
            fence_regs(p1r);
            if (t >= twait) mbar_wait_warp(cb + 8 + t * 4, 0);
            wg_wait<0>();
            fence_regs(o);
            wg_fence();
            mma_qk<0>(s, q, dc + CHD);
            wg_commit();
            mma_pv<1>(o, p1r, dc);
            wg_commit();
            wg_wait<1>();
            fence_regs(s);
            do_exp<0>(s, p0r, cM);
            fence_regs(p0r);
            wg_wait<0>();
            fence_regs(o);
            dc += CHD;
        }
        wg_fence();
        mma_qk<1>(s, q, dc);
        wg_commit();
        mma_pv<0>(o, p0r, dc);
        wg_commit();
        wg_wait<1>();
        fence_regs(s);
        do_exp<8>(s, p1r, cM);
        fence_regs(p1r);
        wg_fence();
        mma_pv<1>(o, p1r, dc);
        wg_commit();
        wg_wait<0>();
        fence_regs(o);
        float4* part = (float4*)(sgen + K2_PART_OFF + tid * 16);
        if (un == 0) {
            part[0] = make_float4(o[0], o[1], o[2], o[3]);
            part[512] = make_float4(o[4], o[5], o[6], o[7]);
            part[1024] = make_float4(o[8], o[9], o[10], o[11]);
        }
        if (un == 2) {
            const float4 a = part[0], b = part[512], d = part[1024];
            o[0] += a.x; o[1] += a.y; o[2] += a.z; o[3] += a.w;
            o[4] += b.x; o[5] += b.y; o[6] += b.z; o[7] += b.w;
            o[8] += d.x; o[9] += d.y; o[10] += d.z; o[11] += d.w;
        }
        if (un != 0) {
            float amax = 0.f, chk = 0.f;
#pragma unroll
            for (int i = 0; i < 12; i++) {
                amax = fmaxf(amax, fabsf(o[i]));
                chk += o[i] * 0.f;
            }
            bool ok = (amax <= 1e37f) && (chk == 0.f);
            if (c == 2) ok = ok && (o[8] >= 1e-18f) && (o[10] >= 1e-18f);
            if (!ok) atomicOr((uint32_t*)(sgen + K2_FLAG_OFF), 1u << mt);
            store_o(o, mt);
        }
        if ((tid & 255) == 0) TSTAMP(1, 3 + un + (tid >> 8) * 5);
    }
    __syncthreads();
    const uint32_t redo = __shfl_sync(0xffffffffu, *(volatile uint32_t*)(sgen + K2_FLAG_OFF), 0);
    if (redo) {
#pragma unroll 1
        for (int mt = 2 * wg; mt < 2 * wg + 2; mt++) {
            if (!((redo >> mt) & 1)) continue;
            load_q(q, mt);
            attn_safe(o, q, d0, bars);
            store_o(o, mt);
        }
    }
}

constexpr int K3_THREADS = 288;
constexpr int K3_NA = 7;
constexpr int K3_NB = 5;
constexpr int K3_PACE = 2;
constexpr int K3_LEAD = 2;
constexpr int K3_BOFF = K3_NA * 16384;
constexpr int K3_XCH = 3 * 16384;
constexpr int K3_BARS = K3_BOFF + K3_NB * 20480;
constexpr int K3_SMEM = K3_BARS + 1024 + 256;
__device__ __forceinline__ void k3_load_w(uint32_t dst, const CUtensorMap* t64, const CUtensorMap* t32, int col0, int k0,
                                          uint32_t bar) {
    mbar_expect_tx(bar, 20480);
    tma_2d(dst, t64, col0, k0, bar);
    tma_2d(dst + 8192, t64, col0 + 64, k0, bar);
    tma_2d(dst + 16384, t32, col0 + 128, k0, bar);
}

__global__ void __launch_bounds__(K3_THREADS, 1)
k3_out(const __grid_constant__ CUtensorMap tmO, const __grid_constant__ CUtensorMap tmWoA,
       const __grid_constant__ CUtensorMap tmWoB, const __grid_constant__ CUtensorMap tmWoA2,
       const __grid_constant__ CUtensorMap tmWoB2, __nv_bfloat16* __restrict__ out) {
    extern __shared__ uint8_t smem_raw[];
    const uint32_t sbase = (smem_u32(smem_raw) + 1023u) & ~1023u;
    uint8_t* sgen = smem_raw + (sbase - smem_u32(smem_raw));
    const uint32_t bars = sbase + K3_BARS;
    const int tid = threadIdx.x, warp = tid >> 5, lane = tid & 31;
    const uint32_t rank = cluster_rank();
    const int p = blockIdx.x >> 1;
    const int rb = p >> 2, cb = p & 3;
    if (tid == 0) TSTAMP(2, 0);
    if (tid == 257) prefetch_tmap(&tmO);
    if (tid == 256) {
        for (int s = 0; s < 10; s++) mbar_init(bars + s * 8, 2);
        for (int s = 0; s < 5; s++) mbar_init(bars + 96 + s * 8, 8);
        mbar_init(bars + 144, 1);
        mbar_init(bars + 152, 8);
        fence_barrier_init();
        fence_proxy_async();
        mbar_expect_tx(bars + 144, 20480);
        for (int kb = 0; kb < K3_NB; kb++)
            k3_load_w(sbase + K3_BOFF + kb * 20480, rank ? &tmWoB : &tmWoA, rank ? &tmWoB2 : &tmWoA2, cb * 160, kb * 64, bars + kb * 8);
    }
    __syncthreads();
    cluster_arrive_relaxed();
    if (warp == 8) {
        if (lane == 0) {
            griddep_wait();
            TSTAMP(2, 1);
            for (int kb = 0; kb < K3_NA; kb++) {
                if (kb == K3_PACE) mbar_wait(bars, 0);
                mbar_expect_tx(bars + kb * 8, 16384);
                tma_2d(sbase + kb * 16384, &tmO, (int)rank * DM + kb * 64, rb * 128, bars + kb * 8);
            }
            for (int i = 0; i < 5; i++) {
                mbar_wait(bars + 96 + i * 8, 0);
                if (K3_NB + i < 10)
                    k3_load_w(sbase + K3_BOFF + i * 20480, rank ? &tmWoB : &tmWoA, rank ? &tmWoB2 : &tmWoA2, cb * 160,
                              (K3_NB + i) * 64, bars + (K3_NB + i) * 8);
                if (K3_NA + i < 10) {
                    mbar_expect_tx(bars + (K3_NA + i) * 8, 16384);
                    tma_2d(sbase + i * 16384, &tmO, (int)rank * DM + (K3_NA + i) * 64, rb * 128, bars + (K3_NA + i) * 8);
                }
            }
        }
        __syncwarp();
        cluster_wait();
    } else {
        const int wg = warp >> 2;
        const int r = rb * 128 + warp * 16 + (lane >> 2);
        const float g0 = __ldcg(g_gate + r), g1 = __ldcg(g_gate + r + 8);
        const uint64_t dA0 = make_desc(sbase + wg * 8192, 16, 1024, 1);
        const uint64_t dB0 = make_desc(sbase + K3_BOFF, 8192, 1024, 1);
        const uint64_t dB1 = make_desc(sbase + K3_BOFF + 16384, 4096, 512, 2);
        const float m0 = rank ? 1.f - g0 : g0, m1 = rank ? 1.f - g1 : g1;
        float acc0[64], acc1[16];
#pragma unroll
        for (int i = 0; i < 64; i++) acc0[i] = 0.f;
#pragma unroll
        for (int i = 0; i < 16; i++) acc1[i] = 0.f;
        fence_regs(acc0);
        fence_regs(acc1);
        cluster_wait();
        if (wg == (int)rank) named_bar_sync(2, 256);
#pragma unroll 1
        for (int kb = 0; kb < 10; kb++) {
            const int sa = (kb >= K3_NA) ? kb - K3_NA : kb, sb = (kb >= K3_NB) ? kb - K3_NB : kb;
            mbar_wait_warp(bars + kb * 8, 0);
            if (tid == 0 && (kb < 6 || kb > 7)) TSTAMP(2, 2 + kb);
            wg_fence();
#pragma unroll
            for (int kk = 0; kk < 4; kk++) {
                wgmma_n128_ss_tb(acc0, dA0 + (uint64_t)(sa * 1024 + kk * 2), dB0 + (uint64_t)(sb * 1280 + kk * 128));
                wgmma_n32_ss_tb(acc1, dA0 + (uint64_t)(sa * 1024 + kk * 2), dB1 + (uint64_t)(sb * 1280 + kk * 64));
            }
            wg_commit();
            if (wg != (int)rank && kb == K3_LEAD - 1) asm volatile("bar.arrive 2, 256;" ::: "memory");
            wg_wait<1>();
            if (lane == 0) {
                if (kb >= 1 && kb <= 5) mbar_arrive(bars + 96 + (kb - 1) * 8);
                if (kb == 6) mbar_arrive_remote(bars + 152, rank ^ 1);
            }
        }
        wg_wait<0>();
        fence_regs(acc0);
        fence_regs(acc1);
        float acc[80];
#pragma unroll
        for (int i = 0; i < 64; i++) acc[i] = acc0[i];
#pragma unroll
        for (int i = 0; i < 16; i++) acc[64 + i] = acc1[i];
        if (tid == 0) TSTAMP(2, 12);
        const int t128 = tid & 127;
        if (wg != (int)rank) {
            uint32_t dst, rbar;
            asm volatile("mapa.shared::cluster.u32 %0, %1, %2;" : "=r"(dst) : "r"(sbase + K3_XCH + t128 * 16), "r"(rank ^ 1));
            asm volatile("mapa.shared::cluster.u32 %0, %1, %2;" : "=r"(rbar) : "r"(bars + 144), "r"(rank ^ 1));
            mbar_wait_cluster(bars + 152, 0);
#pragma unroll
            for (int i = 0; i < 10; i++)
                asm volatile("st.async.weak.shared::cluster.mbarrier::complete_tx::bytes.v4.b32 [%0], {%1, %2, %3, %4}, [%5];"
                             ::"r"(dst + i * 2048), "r"(pack_bf16(acc[8 * i] * m0, acc[8 * i + 1] * m0)),
                               "r"(pack_bf16(acc[8 * i + 2] * m1, acc[8 * i + 3] * m1)),
                               "r"(pack_bf16(acc[8 * i + 4] * m0, acc[8 * i + 5] * m0)),
                               "r"(pack_bf16(acc[8 * i + 6] * m1, acc[8 * i + 7] * m1)), "r"(rbar) : "memory");
        } else {
            uint8_t* stg = sgen + (((warp & 3) == 3) ? 6 : (warp & 3)) * 16384 + wg * 8192;
            const int rr = lane >> 2, c = lane & 3;
            named_bar_sync(1, 128);
            if (t128 == 0) TSTAMP(2, 14);
            mbar_wait_cluster(bars + 144, 0);
            if (t128 == 0) TSTAMP(2, 9);
#pragma unroll
            for (int i = 0; i < 10; i++) {
                const uint4 v = *(const uint4*)(sgen + K3_XCH + t128 * 16 + i * 2048);
                uint8_t* d0 = stg + rr * 336 + i * 32 + c * 4;
                *(uint32_t*)(d0) = pack_bf16(fmaf(m0, acc[8 * i], bf_lo(v.x)), fmaf(m0, acc[8 * i + 1], bf_hi(v.x)));
                *(uint32_t*)(d0 + 8 * 336) = pack_bf16(fmaf(m1, acc[8 * i + 2], bf_lo(v.y)), fmaf(m1, acc[8 * i + 3], bf_hi(v.y)));
                *(uint32_t*)(d0 + 16) = pack_bf16(fmaf(m0, acc[8 * i + 4], bf_lo(v.z)), fmaf(m0, acc[8 * i + 5], bf_hi(v.z)));
                *(uint32_t*)(d0 + 8 * 336 + 16) = pack_bf16(fmaf(m1, acc[8 * i + 6], bf_lo(v.w)), fmaf(m1, acc[8 * i + 7], bf_hi(v.w)));
            }
            __syncwarp();
            if (t128 == 0) TSTAMP(2, 8);
            __nv_bfloat16* ob = out + (size_t)(rb * 128 + warp * 16) * DM + cb * 160;
#pragma unroll 2
            for (int it = 0; it < 10; it++) {
                const int idx = it * 32 + lane;
                const int row = idx / 20, ch = idx % 20;
                *(uint4*)(ob + (size_t)row * DM + ch * 8) = *(const uint4*)(stg + row * 336 + ch * 16);
            }
            if (t128 == 0) TSTAMP(2, 13);
        }
    }
}

typedef CUresult (*PFN_encodeTiled)(CUtensorMap*, CUtensorMapDataType, cuuint32_t, void*, const cuuint64_t*,
                                    const cuuint64_t*, const cuuint32_t*, const cuuint32_t*, CUtensorMapInterleave,
                                    CUtensorMapSwizzle, CUtensorMapL2promotion, CUtensorMapFloatOOBfill);

void encode(PFN_encodeTiled fn, CUtensorMap* tm, const void* ptr, int rank, const cuuint64_t* dims,
            const cuuint64_t* strides, const cuuint32_t* box, CUtensorMapSwizzle swz) {
    cuuint32_t es[3] = {1, 1, 1};
    fn(tm, CU_TENSOR_MAP_DATA_TYPE_BFLOAT16, (cuuint32_t)rank, const_cast<void*>(ptr), dims, strides, box, es,
       CU_TENSOR_MAP_INTERLEAVE_NONE, swz, CU_TENSOR_MAP_L2_PROMOTION_L2_256B, CU_TENSOR_MAP_FLOAT_OOB_FILL_NONE);
}

}

#define USE_PDL 1

extern "C" void kernel_launch(void* const* d_in, const int* in_sizes, int n_in, void* d_out, int out_size) {
    (void)in_sizes; (void)n_in; (void)out_size;
    const __nv_bfloat16* x = (const __nv_bfloat16*)d_in[0];
    const __nv_bfloat16* wq = (const __nv_bfloat16*)d_in[1];
    const __nv_bfloat16* wk = (const __nv_bfloat16*)d_in[2];
    const __nv_bfloat16* wv = (const __nv_bfloat16*)d_in[3];
    const __nv_bfloat16* woA = (const __nv_bfloat16*)d_in[4];
    const __nv_bfloat16* wqkv = (const __nv_bfloat16*)d_in[6];
    const __nv_bfloat16* woB = (const __nv_bfloat16*)d_in[7];
    const __nv_bfloat16* gate_w = (const __nv_bfloat16*)d_in[8];
    __nv_bfloat16* out = (__nv_bfloat16*)d_out;

    static PFN_encodeTiled enc = nullptr;
    if (!enc) {
        void* fp = nullptr;
        cudaDriverEntryPointQueryResult qr;
        cudaGetDriverEntryPoint("cuTensorMapEncodeTiled", &fp, cudaEnableDefault, &qr);
        enc = (PFN_encodeTiled)fp;
        cudaFuncSetAttribute(k1_proj, cudaFuncAttributeMaxDynamicSharedMemorySize, K1_SMEM);
        cudaFuncSetAttribute(k2_attn, cudaFuncAttributeMaxDynamicSharedMemorySize, K2_SMEM);
        cudaFuncSetAttribute(k3_out, cudaFuncAttributeMaxDynamicSharedMemorySize, K3_SMEM);
    }
    void* pO = nullptr;
    cudaGetSymbolAddress(&pO, g_O);

    void* pQKV = nullptr;
    cudaGetSymbolAddress(&pQKV, g_QKVB);
    CUtensorMap tmX, tmWq, tmWqkv, tmO, tmWoA, tmWoB, tmWoA2, tmWoB2, tmLkv, tmLq, tmQo, tmQKVo;
    void* pQ = nullptr;
    cudaGetSymbolAddress(&pQ, g_Q);
    {
        cuuint64_t d[2] = {1920, 2048}, s[1] = {3840};
        cuuint32_t b[2] = {176, 32}, b2[2] = {176, 16};
        encode(enc, &tmLkv, pQKV, 2, d, s, b, CU_TENSOR_MAP_SWIZZLE_NONE);
        encode(enc, &tmLq, pQKV, 2, d, s, b2, CU_TENSOR_MAP_SWIZZLE_NONE);
        cuuint64_t dq[2] = {640, 2048}, sq[1] = {1280};
        cuuint32_t bo[2] = {64, 16};
        encode(enc, &tmQKVo, pQKV, 2, d, s, bo, CU_TENSOR_MAP_SWIZZLE_128B);
        encode(enc, &tmQo, pQ, 2, dq, sq, bo, CU_TENSOR_MAP_SWIZZLE_128B);
    }
    {
        cuuint64_t d[2] = {640, 2048}, s[1] = {1280};
        cuuint32_t b[2] = {64, 128};
        encode(enc, &tmX, x, 2, d, s, b, CU_TENSOR_MAP_SWIZZLE_128B);
    }
    {
        cuuint64_t d[3] = {64, 640, 10}, s[2] = {1280, 128};
        cuuint32_t b[3] = {64, 64, 5};
        encode(enc, &tmWq, wq, 3, d, s, b, CU_TENSOR_MAP_SWIZZLE_128B);
    }
    {
        cuuint64_t d[3] = {64, 640, 30}, s[2] = {3840, 128};
        cuuint32_t b[3] = {64, 64, 5};
        encode(enc, &tmWqkv, wqkv, 3, d, s, b, CU_TENSOR_MAP_SWIZZLE_128B);
    }
    {
        cuuint64_t d[2] = {1280, 2048}, s[1] = {2560};
        cuuint32_t b[2] = {64, 128};
        encode(enc, &tmO, pO, 2, d, s, b, CU_TENSOR_MAP_SWIZZLE_128B);
    }
    {
        cuuint64_t d[2] = {640, 640}, s[1] = {1280};
        cuuint32_t b[2] = {64, 64}, b2[2] = {32, 64};
        encode(enc, &tmWoA, woA, 2, d, s, b, CU_TENSOR_MAP_SWIZZLE_128B);
        encode(enc, &tmWoB, woB, 2, d, s, b, CU_TENSOR_MAP_SWIZZLE_128B);
        encode(enc, &tmWoA2, woA, 2, d, s, b2, CU_TENSOR_MAP_SWIZZLE_64B);
        encode(enc, &tmWoB2, woB, 2, d, s, b2, CU_TENSOR_MAP_SWIZZLE_64B);
    }

    cudaStream_t st = cudaStreamPerThread;
    cudaLaunchAttribute at[2];
    cudaLaunchConfig_t cfg = {};
    cfg.stream = st;
    cfg.attrs = at;
    cfg.gridDim = dim3(132); cfg.blockDim = dim3(K1_THREADS); cfg.dynamicSmemBytes = K1_SMEM; cfg.numAttrs = 0;
    cudaLaunchKernelEx(&cfg, k1_proj, tmX, tmWq, tmWqkv, tmQo, tmQKVo, wk, wv, gate_w);
    at[0].id = cudaLaunchAttributeProgrammaticStreamSerialization;
    at[0].val.programmaticStreamSerializationAllowed = 1;
    cfg.gridDim = dim3(132); cfg.blockDim = dim3(K2_THREADS); cfg.dynamicSmemBytes = K2_SMEM; cfg.numAttrs = USE_PDL ? 1 : 0;
    cudaLaunchKernelEx(&cfg, k2_attn, tmLkv, tmLq);
    at[0].id = cudaLaunchAttributeClusterDimension;
    at[0].val.clusterDim.x = 2; at[0].val.clusterDim.y = 1; at[0].val.clusterDim.z = 1;
    at[1].id = cudaLaunchAttributeProgrammaticStreamSerialization;
    at[1].val.programmaticStreamSerializationAllowed = 1;
    cfg.gridDim = dim3(128); cfg.blockDim = dim3(K3_THREADS); cfg.dynamicSmemBytes = K3_SMEM; cfg.numAttrs = USE_PDL ? 2 : 1;
    cudaLaunchKernelEx(&cfg, k3_out, tmO, tmWoA, tmWoB, tmWoA2, tmWoB2, out);
}
```
